```python
import torch

def _softmax(x, axis=-1):
    return torch.softmax(x, dim=axis)
def _gelu(x):
    return torch.nn.functional.gelu(x, approximate="tanh")
def _silu(x):
    return torch.nn.functional.silu(x)
def _sigmoid(x):
    return torch.sigmoid(x)
def _layernorm(x, axis=-1, eps=1e-5):
    m = x.mean(dim=axis, keepdim=True)
    v = x.var(dim=axis, keepdim=True, unbiased=False)
    return (x - m) / torch.sqrt(v + eps)
def _scatter_add(tgt, idx, src, axis=0):
    return tgt.clone().index_add_(axis, idx, src)
def _segment_sum(src, seg, n):
    out = torch.zeros((n,) + src.shape[1:], dtype=src.dtype)
    return out.index_add_(0, seg, src)
def _pad(x, pw):
    flat = tuple(v for pair in reversed(pw) for v in pair)
    return torch.nn.functional.pad(x, flat)

kernel_name = 'standalone__detection_seg_fpn_lateral__vision'

def setup_inputs():

    _w = (lambda a: (lambda t: t.to(torch.bfloat16) if t.is_floating_point() else t)(torch.as_tensor(a)))
    H = W = (512 // 2) * 2
    C = 96
    k = 3
    return {
        "c_fine": _w((lambda *s: torch.randn(*s, dtype=torch.bfloat16) * 0.05)(1, H, W, C)),
        "p_coarse": _w((lambda *s: torch.randn(*s, dtype=torch.bfloat16) * 0.05)(1, H // 2, W // 2, C)),
        "w_lat": _w((lambda *s: torch.randn(*s, dtype=torch.bfloat16) * 0.05)(C, C)),
        "w_out": _w((lambda *s: torch.randn(*s, dtype=torch.bfloat16) * 0.05)(k, k, C, C)),
    }

def reference(c_fine, p_coarse, w_lat, w_out):
    B, H, W, C = c_fine.shape
    k = 3
    lat = torch.einsum("bhwc,cd->bhwd", c_fine, w_lat)
    up = (lambda x, n, axis: torch.repeat_interleave(x, n, dim=axis))((lambda x, n, axis: torch.repeat_interleave(x, n, dim=axis))(p_coarse, 2, axis=1), 2, axis=2)
    m = lat + up
    pad = k // 2
    mp = _pad(m, ((0, 0), (pad, pad), (pad, pad), (0, 0)))
    o = None
    for di in range(k):
        for dj in range(k):
            t = torch.einsum("bhwc,cd->bhwd", mp[:, di:di + H, dj:dj + W, :], w_out[di, dj])
            o = t if o is None else o + t
    return o
```

```cpp
#include <cuda_runtime.h>
#include <cuda_bf16.h>
#include <stdint.h>

#define TS(k)
#define FENCE_C fence_async();
namespace {

typedef __nv_bfloat16 bf16;

constexpr int IMG_H = 512, IMG_W = 512;
constexpr int STEPS = 16;
constexpr int U_TILE = 3072;
constexpr int U_BYTES = 36 * U_TILE;
constexpr int WL_TILE = 1536;
constexpr int WL_BYTES = 6 * WL_TILE;
constexpr int PLANE = 130 * 16;
constexpr int TROW = 6 * PLANE;
constexpr int PAIR = 2 * TROW;
constexpr int XBUF = 12288;
constexpr int OFF_U = 0;
constexpr int OFF_WL = OFF_U + U_BYTES;
constexpr int OFF_T = OFF_WL + WL_BYTES;
constexpr int OFF_X = OFF_T + 2 * PAIR;
constexpr int OFF_C = OFF_X + 2 * XBUF;
constexpr int OFF_HM = OFF_C + 128 * 192;
constexpr int OFF_HC = OFF_HM + 2 * 34 * 96;
constexpr int OFF_BAR = OFF_HC + 34 * 192;
constexpr int SMEM_BYTES = OFF_BAR + 256;
constexpr int BAR_FULL = 0;
constexpr int BAR_EMPTY = 3;
constexpr int BAR_XFULL = 6;
constexpr int BAR_XEMPTY = 8;
constexpr int BAR_W = 10;
constexpr int BAR_WL = 11;
constexpr int BAR_C = 12;
constexpr int BAR_H = 20;

template<int TB>
__device__ __forceinline__ void wgmma_ss_n96(float* d, uint64_t da, uint64_t db, int scale_d) {
  asm volatile("{\n.reg .pred p;\nsetp.ne.b32 p, %50, 0;\n"
    "wgmma.mma_async.sync.aligned.m64n96k16.f32.bf16.bf16 "
    "{%0, %1, %2, %3, %4, %5, %6, %7, %8, %9, %10, %11, %12, %13, %14, %15, %16, %17, %18, %19, %20, %21, %22, %23, %24, %25, %26, %27, %28, %29, %30, %31, %32, %33, %34, %35, %36, %37, %38, %39, %40, %41, %42, %43, %44, %45, %46, %47}, "
    "%48, %49, p, 1, 1, 0, %51;\n}\n"
    : "+f"(d[0]), "+f"(d[1]), "+f"(d[2]), "+f"(d[3]), "+f"(d[4]), "+f"(d[5]), "+f"(d[6]), "+f"(d[7]), "+f"(d[8]), "+f"(d[9]), "+f"(d[10]), "+f"(d[11]), "+f"(d[12]), "+f"(d[13]), "+f"(d[14]), "+f"(d[15]), "+f"(d[16]), "+f"(d[17]), "+f"(d[18]), "+f"(d[19]), "+f"(d[20]), "+f"(d[21]), "+f"(d[22]), "+f"(d[23]), "+f"(d[24]), "+f"(d[25]), "+f"(d[26]), "+f"(d[27]), "+f"(d[28]), "+f"(d[29]), "+f"(d[30]), "+f"(d[31]), "+f"(d[32]), "+f"(d[33]), "+f"(d[34]), "+f"(d[35]), "+f"(d[36]), "+f"(d[37]), "+f"(d[38]), "+f"(d[39]), "+f"(d[40]), "+f"(d[41]), "+f"(d[42]), "+f"(d[43]), "+f"(d[44]), "+f"(d[45]), "+f"(d[46]), "+f"(d[47])
    : "l"(da), "l"(db), "r"(scale_d), "n"(TB));
}

template<int TB>
__device__ __forceinline__ void wgmma_ss_n96_init(float* d, uint64_t da, uint64_t db) {
  asm volatile("{\n.reg .pred p;\nsetp.ne.b32 p, 0, 0;\n"
    "wgmma.mma_async.sync.aligned.m64n96k16.f32.bf16.bf16 "
    "{%0, %1, %2, %3, %4, %5, %6, %7, %8, %9, %10, %11, %12, %13, %14, %15, %16, %17, %18, %19, %20, %21, %22, %23, %24, %25, %26, %27, %28, %29, %30, %31, %32, %33, %34, %35, %36, %37, %38, %39, %40, %41, %42, %43, %44, %45, %46, %47}, "
    "%48, %49, p, 1, 1, 0, %50;\n}\n"
    : "=f"(d[0]), "=f"(d[1]), "=f"(d[2]), "=f"(d[3]), "=f"(d[4]), "=f"(d[5]), "=f"(d[6]), "=f"(d[7]), "=f"(d[8]), "=f"(d[9]), "=f"(d[10]), "=f"(d[11]), "=f"(d[12]), "=f"(d[13]), "=f"(d[14]), "=f"(d[15]), "=f"(d[16]), "=f"(d[17]), "=f"(d[18]), "=f"(d[19]), "=f"(d[20]), "=f"(d[21]), "=f"(d[22]), "=f"(d[23]), "=f"(d[24]), "=f"(d[25]), "=f"(d[26]), "=f"(d[27]), "=f"(d[28]), "=f"(d[29]), "=f"(d[30]), "=f"(d[31]), "=f"(d[32]), "=f"(d[33]), "=f"(d[34]), "=f"(d[35]), "=f"(d[36]), "=f"(d[37]), "=f"(d[38]), "=f"(d[39]), "=f"(d[40]), "=f"(d[41]), "=f"(d[42]), "=f"(d[43]), "=f"(d[44]), "=f"(d[45]), "=f"(d[46]), "=f"(d[47])
    : "l"(da), "l"(db), "n"(TB));
}

template<int TB>
__device__ __forceinline__ void wgmma_rs_n48(float* d, uint32_t a0, uint32_t a1, uint32_t a2, uint32_t a3, uint64_t db, int scale_d) {
  asm volatile("{\n.reg .pred p;\nsetp.ne.b32 p, %29, 0;\n"
    "wgmma.mma_async.sync.aligned.m64n48k16.f32.bf16.bf16 "
    "{%0, %1, %2, %3, %4, %5, %6, %7, %8, %9, %10, %11, %12, %13, %14, %15, %16, %17, %18, %19, %20, %21, %22, %23}, "
    "{%24, %25, %26, %27}, %28, p, 1, 1, %30;\n}\n"
    : "+f"(d[0]), "+f"(d[1]), "+f"(d[2]), "+f"(d[3]), "+f"(d[4]), "+f"(d[5]), "+f"(d[6]), "+f"(d[7]), "+f"(d[8]), "+f"(d[9]), "+f"(d[10]), "+f"(d[11]), "+f"(d[12]), "+f"(d[13]), "+f"(d[14]), "+f"(d[15]), "+f"(d[16]), "+f"(d[17]), "+f"(d[18]), "+f"(d[19]), "+f"(d[20]), "+f"(d[21]), "+f"(d[22]), "+f"(d[23])
    : "r"(a0), "r"(a1), "r"(a2), "r"(a3), "l"(db), "r"(scale_d), "n"(TB));
}

template<int TB>
__device__ __forceinline__ void wgmma_rs_n48_init(float* d, uint32_t a0, uint32_t a1, uint32_t a2, uint32_t a3, uint64_t db) {
  asm volatile("{\n.reg .pred p;\nsetp.ne.b32 p, 0, 0;\n"
    "wgmma.mma_async.sync.aligned.m64n48k16.f32.bf16.bf16 "
    "{%0, %1, %2, %3, %4, %5, %6, %7, %8, %9, %10, %11, %12, %13, %14, %15, %16, %17, %18, %19, %20, %21, %22, %23}, "
    "{%24, %25, %26, %27}, %28, p, 1, 1, %29;\n}\n"
    : "=f"(d[0]), "=f"(d[1]), "=f"(d[2]), "=f"(d[3]), "=f"(d[4]), "=f"(d[5]), "=f"(d[6]), "=f"(d[7]), "=f"(d[8]), "=f"(d[9]), "=f"(d[10]), "=f"(d[11]), "=f"(d[12]), "=f"(d[13]), "=f"(d[14]), "=f"(d[15]), "=f"(d[16]), "=f"(d[17]), "=f"(d[18]), "=f"(d[19]), "=f"(d[20]), "=f"(d[21]), "=f"(d[22]), "=f"(d[23])
    : "r"(a0), "r"(a1), "r"(a2), "r"(a3), "l"(db), "n"(TB));
}

__device__ __forceinline__ void wg_fence() { asm volatile("wgmma.fence.sync.aligned;" ::: "memory"); }
__device__ __forceinline__ void wg_commit() { asm volatile("wgmma.commit_group.sync.aligned;" ::: "memory"); }
template<int N> __device__ __forceinline__ void wg_wait() { asm volatile("wgmma.wait_group.sync.aligned %0;" :: "n"(N) : "memory"); }
__device__ __forceinline__ void fence_async() { asm volatile("fence.proxy.async.shared::cta;" ::: "memory"); }

__device__ __forceinline__ uint64_t mkdesc(uint32_t lo, uint32_t hi) { return ((uint64_t)hi << 32) | (uint64_t)lo; }

__device__ __forceinline__ void mbar_init(uint32_t bar, uint32_t cnt) {
  asm volatile("mbarrier.init.shared::cta.b64 [%0], %1;" :: "r"(bar), "r"(cnt) : "memory");
}
__device__ __forceinline__ void mbar_arrive(uint32_t bar) {
  asm volatile("mbarrier.arrive.shared::cta.b64 _, [%0];" :: "r"(bar) : "memory");
}
__device__ __forceinline__ void mbar_arrive_remote(uint32_t rbar) {
  asm volatile("mbarrier.arrive.shared::cluster.b64 _, [%0];" :: "r"(rbar) : "memory");
}
__device__ __forceinline__ void mbar_expect_tx(uint32_t bar, uint32_t bytes) {
  asm volatile("mbarrier.arrive.expect_tx.shared::cta.b64 _, [%0], %1;" :: "r"(bar), "r"(bytes) : "memory");
}
__device__ __forceinline__ void mbar_wait(uint32_t bar, uint32_t parity) {
  uint32_t done;
  int it = 0;
  do {
    asm volatile("{\n.reg .pred p;\nmbarrier.try_wait.parity.shared::cta.b64 p, [%1], %2;\nselp.u32 %0, 1, 0, p;\n}\n"
                 : "=r"(done) : "r"(bar), "r"(parity) : "memory");
    if (++it > (1 << 22)) break;
  } while (!done);
}
__device__ __forceinline__ bool mbar_test(uint32_t bar, uint32_t parity) {
  uint32_t done;
  asm volatile("{\n.reg .pred p;\nmbarrier.test_wait.parity.shared::cta.b64 p, [%1], %2;\nselp.u32 %0, 1, 0, p;\n}\n"
               : "=r"(done) : "r"(bar), "r"(parity) : "memory");
  return __all_sync(0xffffffffu, done != 0);
}
__device__ __forceinline__ uint32_t mapa(uint32_t addr, uint32_t rank) {
  uint32_t r; asm volatile("mapa.shared::cluster.u32 %0, %1, %2;" : "=r"(r) : "r"(addr), "r"(rank)); return r;
}
__device__ __forceinline__ void st_async_v4(uint32_t raddr, uint4 v, uint32_t rbar) {
  asm volatile("st.async.weak.shared::cluster.mbarrier::complete_tx::bytes.v4.b32 [%0], {%1, %2, %3, %4}, [%5];"
               :: "r"(raddr), "r"(v.x), "r"(v.y), "r"(v.z), "r"(v.w), "r"(rbar) : "memory");
}
__device__ __forceinline__ void cluster_arrive() { asm volatile("barrier.cluster.arrive.relaxed.aligned;" ::: "memory"); }
__device__ __forceinline__ void cluster_wait() { asm volatile("barrier.cluster.wait.aligned;" ::: "memory"); }
__device__ __forceinline__ void bar_sync(int id, int n) { asm volatile("bar.sync %0, %1;" :: "r"(id), "r"(n) : "memory"); }

__device__ __forceinline__ void bar_arrive(int id, int n) { asm volatile("bar.arrive %0, %1;" :: "r"(id), "r"(n) : "memory"); }
__device__ __forceinline__ void l2_prefetch(const void* p, uint32_t bytes) {
  asm volatile("cp.async.bulk.prefetch.L2.global [%0], %1;" :: "l"(p), "r"(bytes) : "memory");
}
__device__ __forceinline__ void sts32(uint32_t a, uint32_t v) { asm volatile("st.shared.b32 [%0], %1;" :: "r"(a), "r"(v) : "memory"); }
__device__ __forceinline__ void sts64(uint32_t a, uint32_t v0, uint32_t v1) { asm volatile("st.shared.v2.b32 [%0], {%1, %2};" :: "r"(a), "r"(v0), "r"(v1) : "memory"); }
__device__ __forceinline__ void sts128(uint32_t a, uint32_t v0, uint32_t v1, uint32_t v2, uint32_t v3) {
  asm volatile("st.shared.v4.b32 [%0], {%1, %2, %3, %4};" :: "r"(a), "r"(v0), "r"(v1), "r"(v2), "r"(v3) : "memory");
}
__device__ __forceinline__ uint4 lds128(uint32_t a) {
  uint4 v; asm volatile("ld.shared.v4.b32 {%0, %1, %2, %3}, [%4];" : "=r"(v.x), "=r"(v.y), "=r"(v.z), "=r"(v.w) : "r"(a) : "memory"); return v;
}
__device__ __forceinline__ uint4 ldg128(const void* p) {
  uint4 v; asm volatile("ld.global.nc.L1::no_allocate.v4.b32 {%0, %1, %2, %3}, [%4];" : "=r"(v.x), "=r"(v.y), "=r"(v.z), "=r"(v.w) : "l"(p)); return v;
}
__device__ __forceinline__ void bulk_g2s(uint32_t dst, const void* src, uint32_t bytes, uint32_t bar) {
  asm volatile("cp.async.bulk.shared::cluster.global.mbarrier::complete_tx::bytes [%0], [%1], %2, [%3];"
               :: "r"(dst), "l"(src), "r"(bytes), "r"(bar) : "memory");
}
__device__ __forceinline__ void stg128(void* p, uint4 v) {
  asm volatile("st.global.L1::no_allocate.v4.b32 [%0], {%1, %2, %3, %4};" :: "l"(p), "r"(v.x), "r"(v.y), "r"(v.z), "r"(v.w) : "memory");
}
__device__ __forceinline__ uint2 ldg64(const void* p) {
  uint2 v; asm volatile("ld.global.nc.L1::no_allocate.v2.b32 {%0, %1}, [%2];" : "=r"(v.x), "=r"(v.y) : "l"(p)); return v;
}
__device__ __forceinline__ uint32_t pack2(float lo, float hi) {
  uint32_t r; asm("cvt.rn.bf16x2.f32 %0, %1, %2;" : "=r"(r) : "f"(hi), "f"(lo)); return r;
}
__device__ __forceinline__ float bf_lo(uint32_t w) { return __uint_as_float(w << 16); }
__device__ __forceinline__ float bf_hi(uint32_t w) { return __uint_as_float(w & 0xffff0000u); }
__device__ __forceinline__ uint32_t badd(uint32_t a, uint32_t b) { uint32_t r; asm("add.rn.bf16x2 %0, %1, %2;" : "=r"(r) : "r"(a), "r"(b)); return r; }
__device__ __forceinline__ uint32_t bsub(uint32_t a, uint32_t b) { uint32_t r; asm("sub.rn.bf16x2 %0, %1, %2;" : "=r"(r) : "r"(a), "r"(b)); return r; }

__device__ __forceinline__ uint32_t bfma(uint32_t a, uint32_t b, uint32_t c) { uint32_t r; asm("fma.rn.bf16x2 %0, %1, %2, %3;" : "=r"(r) : "r"(a), "r"(b), "r"(c)); return r; }
__device__ __forceinline__ uint2 lds64(uint32_t a) {
  uint2 v; asm volatile("ld.shared.v2.b32 {%0, %1}, [%2];" : "=r"(v.x), "=r"(v.y) : "r"(a) : "memory"); return v;
}
__device__ __forceinline__ void load_frags(uint4 (&f)[3][2], uint32_t a0, uint32_t a1) {
#pragma unroll
  for (int a = 0; a < 3; a++) { f[a][0] = lds128(a0 + 64 * a); f[a][1] = lds128(a1 + 64 * a); }
}
__device__ __forceinline__ void lateral_issue(float (&acc)[24], const uint4 (&f)[3][2], uint32_t wl_lo) {
  const uint32_t hi = (128u >> 4);
  const uint32_t lbo = (768u >> 4) << 16;
  wg_fence();
#pragma unroll
  for (int a = 0; a < 3; a++) {
    const uint64_t d0 = mkdesc((wl_lo + (2 * a * WL_TILE >> 4)) | lbo, hi), d1 = mkdesc((wl_lo + ((2 * a + 1) * WL_TILE >> 4)) | lbo, hi);
    if (a == 0) wgmma_rs_n48_init<1>(acc, f[a][0].x, f[a][1].x, f[a][0].z, f[a][1].z, d0);
    else wgmma_rs_n48<1>(acc, f[a][0].x, f[a][1].x, f[a][0].z, f[a][1].z, d0, 1);
    wgmma_rs_n48<1>(acc, f[a][0].y, f[a][1].y, f[a][0].w, f[a][1].w, d1, 1);
  }
  wg_commit();
}

__global__ void __cluster_dims__(2, 1, 1) __launch_bounds__(512, 1)
fpn_kernel(const bf16* __restrict__ gc, const bf16* __restrict__ gp, const bf16* __restrict__ gwl,
           const bf16* __restrict__ gwo, bf16* __restrict__ gout) {
  extern __shared__ __align__(1024) uint8_t smem[];
  const uint32_t sb = (uint32_t)__cvta_generic_to_shared(smem);
  const int tid = threadIdx.x, lane = tid & 31, g = lane >> 2, q = lane & 3;
  const int wg = __shfl_sync(0xffffffffu, tid >> 7, 0), warp = __shfl_sync(0xffffffffu, (tid >> 5) & 3, 0);
  uint32_t rank; asm("mov.u32 %0, %%cluster_ctarank;" : "=r"(rank));
  const int cl = blockIdx.x >> 1;
  const int x0 = (cl & 3) * 128;
  const int i0 = (cl >> 2) * STEPS;
  const uint32_t bars = sb + OFF_BAR;

  TS(0);
  if (tid == 0) {
    for (int k = 0; k < 2; k++) { mbar_init(bars + (BAR_FULL + k) * 8, 8); mbar_init(bars + (BAR_EMPTY + k) * 8, 8); }
    for (int k = 0; k < 2; k++) { mbar_init(bars + (BAR_XFULL + k) * 8, 1); mbar_init(bars + (BAR_XEMPTY + k) * 8, 4); }
    mbar_init(bars + BAR_W * 8, 1);
    asm volatile("fence.mbarrier_init.release.cluster;" ::: "memory");
    mbar_expect_tx(bars + BAR_W * 8, 9 * 9216);
#pragma unroll 1
    for (int t = 8; t >= 0; t--)
      bulk_g2s(t == 8 ? sb + OFF_U : sb + OFF_T + t * 9216, gwo + (t * 96 + 48 * (int)rank) * 96, 9216, bars + BAR_W * 8);
  }
  __syncwarp();
  cluster_arrive();

  if (wg < 2) {
    const int s = wg;
    {
      const uint32_t off0 = rank ? 3 * 9 * U_TILE : 2 * 9 * U_TILE;
      const uint32_t off3 = rank ? 2 * 9 * U_TILE : 3 * 9 * U_TILE;
      const uint32_t sgn2 = rank ? 0x80008000u : 0u;
      bar_sync(1, 256);
      mbar_wait(bars + BAR_W * 8, 0);
      TS(21);
#pragma unroll 1
      for (int item = wg * 4 + warp; item < 54; item += 8) {
        if ((item >> 3) == 4) bar_sync(6, 512);
        const int dr = item / 18, dj = 2 - dr, rem = item - 18 * dr, kg = rem / 3, a = rem - 3 * kg;
        const uint32_t so = (8 * kg + g) * 192 + a * 64 + q * 16, src = sb + OFF_T + dj * 9216 + so;
        const uint4 v0 = lds128(src), v1 = lds128(src + 3 * 9216), v2 = lds128(dj == 2 ? sb + OFF_U + so : src + 6 * 9216);
        const uint32_t base = sb + OFF_U + (dj * 3 + (kg >> 1)) * U_TILE + (kg & 1) * 1536 + (4 * a) * 128 + g * 16 + q * 4;
        const uint32_t w0[4] = {v0.x, v0.y, v0.z, v0.w};
        const uint32_t w1[4] = {v1.x, v1.y, v1.z, v1.w};
        const uint32_t w2[4] = {v2.x, v2.y, v2.z, v2.w};
#pragma unroll
        for (int i = 0; i < 4; i++) {
          const float sl = bf_lo(w0[i]) + bf_lo(w2[i]), sh = bf_hi(w0[i]) + bf_hi(w2[i]);
          const float ml = bf_lo(w1[i]), mh = bf_hi(w1[i]);
          const uint32_t u1 = pack2((sl + ml) * 0.5f, (sh + mh) * 0.5f);
          const uint32_t u2 = pack2((sl - ml) * 0.5f, (sh - mh) * 0.5f) ^ sgn2;
          sts32(base + i * 128, u1);
          sts32(base + i * 128 + 9 * U_TILE, u2);
          sts32(base + i * 128 + off0, w0[i]);
          sts32(base + i * 128 + off3, w2[i] ^ 0x80008000u);
        }
      }
      cluster_wait();
      fence_async();
      bar_sync(1, 256);
    }
    TS(1);

    const uint32_t a_hi = 128u >> 4, a_lbo = ((uint32_t)PLANE >> 4) << 16;
    const uint32_t b_hi = 128u >> 4, b_lbo = (1536u >> 4) << 16;
    const uint32_t t_lo = (((sb & 0x3FFFFu) + OFF_T + s * 64 * 16) >> 4) | a_lbo;
    const uint32_t u_lo = (((sb & 0x3FFFFu) + OFF_U) >> 4) | b_lbo;
    const uint32_t xloc = sb + OFF_X + s * XBUF + (tid & 127) * 16;
    const uint32_t xrem = mapa(xloc, rank ^ 1);
    const uint32_t xfull_l = bars + (BAR_XFULL + s) * 8, xempty_l = bars + (BAR_XEMPTY + s) * 8;
    const uint32_t xfull_r = mapa(xfull_l, rank ^ 1), xempty_r = mapa(xempty_l, rank ^ 1);
    bf16* optr = gout + ((size_t)((2 * i0 + (int)rank) * IMG_W + x0 + 64 * s + 16 * warp + g) * 96 + 8 * q) - 2 * IMG_W * 96;

    if (lane == 0) {
      for (int k = 0; k < 2; k++) mbar_arrive(bars + (BAR_EMPTY + k) * 8);
      mbar_arrive_remote(xempty_r);
    }
    float X[48], Y[48];
    auto finalize = [&](int i) {
      if ((tid & 127) == 0) mbar_expect_tx(xfull_l, XBUF);
      optr += 2 * IMG_W * 96;
      asm volatile("" : "+l"(optr));
      mbar_wait(xfull_l, i & 1);
#pragma unroll
      for (int h = 0; h < 2; h++)
#pragma unroll
        for (int a = 0; a < 3; a++) {
          const uint4 r = lds128(xloc + (h * 3 + a) * 2048);
          uint4 v;
          v.x = pack2(X[16 * a + 0 + 2 * h] + bf_lo(r.x), X[16 * a + 1 + 2 * h] + bf_hi(r.x));
          v.y = pack2(X[16 * a + 4 + 2 * h] + bf_lo(r.y), X[16 * a + 5 + 2 * h] + bf_hi(r.y));
          v.z = pack2(X[16 * a + 8 + 2 * h] + bf_lo(r.z), X[16 * a + 9 + 2 * h] + bf_hi(r.z));
          v.w = pack2(X[16 * a + 12 + 2 * h] + bf_lo(r.w), X[16 * a + 13 + 2 * h] + bf_hi(r.w));
          stg128(optr + h * 8 * 96 + 32 * a, v);
        }
      __syncwarp();
      if (lane == 0 && i + 1 < STEPS) mbar_arrive_remote(xempty_r);
    };
#define CONV9(ACC, AOFF, ROLE, INIT)                                                                   \
    _Pragma("unroll") for (int dj = 0; dj < 3; dj++)                                                   \
    _Pragma("unroll") for (int ks = 0; ks < 3; ks++) {                                                 \
      const uint64_t da = mkdesc(ta + (((AOFF) + ks * 2 * PLANE + dj * 16) >> 4), a_hi);               \
      const uint64_t db = mkdesc(u_lo + (((ROLE) * 9 + dj * 3 + ks) * U_TILE >> 4), b_hi);             \
      if (INIT && (dj | ks) == 0) wgmma_ss_n96_init<1>(ACC, da, db); else wgmma_ss_n96<1>(ACC, da, db, 1); \
    }                                                                                                  \
    wg_commit();

#pragma unroll 1
    for (int i = 0; i < STEPS; i++) {
      mbar_wait(bars + BAR_FULL * 8, i & 1);
      FENCE_C
      TS(2 + i);
      if (s == 1) bar_sync(3, 256);
      {
        const uint32_t ta = t_lo;
        wg_fence();
        CONV9(Y, TROW, 1, true)
        if (i > 0) finalize(i - 1);
        else if (s == 0) wg_wait<0>();
        if (s == 0) bar_arrive(3, 256);
        wg_fence();
        CONV9(X, 0, 0, true)
      }
      wg_wait<0>();
      if (lane == 0) mbar_arrive(bars + BAR_EMPTY * 8);
#pragma unroll
      for (int k = 0; k < 48; k++)
        asm volatile("add.f32 %0, %0, %1;\nfma.rn.f32 %1, %1, 0fC0000000, %0;" : "+f"(X[k]), "+f"(Y[k]) :: "memory");
      mbar_wait(bars + (BAR_FULL + 1) * 8, i & 1);
      FENCE_C
      {
        const uint32_t ta = t_lo + (PAIR >> 4);
        wg_fence();
        CONV9(Y, TROW, 3, false)
        CONV9(X, 0, 2, false)
      }
      mbar_wait(xempty_l, i & 1);
      wg_wait<1>();
#pragma unroll
      for (int h = 0; h < 2; h++)
#pragma unroll
        for (int a = 0; a < 3; a++) {
          uint4 v;
          v.x = pack2(Y[16 * a + 0 + 2 * h], Y[16 * a + 1 + 2 * h]);
          v.y = pack2(Y[16 * a + 4 + 2 * h], Y[16 * a + 5 + 2 * h]);
          v.z = pack2(Y[16 * a + 8 + 2 * h], Y[16 * a + 9 + 2 * h]);
          v.w = pack2(Y[16 * a + 12 + 2 * h], Y[16 * a + 13 + 2 * h]);
          st_async_v4(xrem + (h * 3 + a) * 2048, v, xfull_r);
        }
      wg_wait<0>();
      if (lane == 0) mbar_arrive(bars + (BAR_EMPTY + 1) * 8);
    }
    finalize(STEPS - 1);
    TS(20);
  } else {
    const int s = wg - 2;
    const int pt = tid & 127;
    const uint32_t wl_lo = ((sb & 0x3FFFFu) + OFF_WL) >> 4;
    const int chb = 48 * (int)rank;
    const uint32_t odd = g & 1;
    const uint32_t cbar = bars + (BAR_C + 4 * s + warp) * 8;
    const uint32_t cbuf = sb + OFF_C + (64 * s + 16 * warp) * 192;
    const char* csrc = (const char*)gc + (size_t)(x0 + 64 * s + 16 * warp) * 192;
    auto tma_row = [&](int yy) {
      const int y = min(max(yy, 0), IMG_H - 1);
      mbar_expect_tx(cbar, 16 * 192);
      bulk_g2s(cbuf, csrc + (size_t)y * (IMG_W * 192), 16 * 192, cbar);
    };
    const int hx = x0 + (s ? 128 : -1);
    const uint32_t hbar = bars + (BAR_H + 4 * s + warp) * 8;
    const uint32_t hcbuf = s ? sb + OFF_HC : sb + OFF_U + 3 * 9 * U_TILE;
    if (lane == 0) {
      mbar_init(cbar, 1);
      mbar_init(hbar, 1);
      if (tid == 256) mbar_init(bars + BAR_WL * 8, 1);
      asm volatile("fence.mbarrier_init.release.cluster;" ::: "memory");
      if (tid == 256) {
        mbar_expect_tx(bars + BAR_WL * 8, 2 * 9216);
        bulk_g2s(sb + OFF_U + 9 * U_TILE, gwl, 9216, bars + BAR_WL * 8);
        bulk_g2s(sb + OFF_U + 18 * U_TILE, gwl + 48 * 96, 9216, bars + BAR_WL * 8);
      }
      tma_row(2 * i0 - 1);
      mbar_expect_tx(hbar, min(max(34 - 16 * warp, 0), 16) * 288);
    }
    __syncwarp();
    {
      const int r = 16 * warp + (lane & 15);
      const int x = min(max(hx, 0), IMG_W - 1), y = min(max(2 * i0 - 1 + r, 0), IMG_H - 1);
      if (r < 34) {
        if (lane < 16) bulk_g2s(hcbuf + r * 192, gc + (size_t)(y * IMG_W + x) * 96, 192, hbar);
        else bulk_g2s(sb + OFF_HM + (s * 34 + r) * 96, gp + ((size_t)((y >> 1) * (IMG_W / 2) + (x >> 1)) * 96 + chb), 96, hbar);
      }
    }
    const uint32_t poff4 = (((x0 >> 1) + 32 * s + 8 * warp + g) * 96 + chb + 8 * q) * 2;
    const uint32_t poff2 = (((x0 >> 1) + 32 * s + 8 * warp + g) * 96 + chb + 32 + 4 * q) * 2;

    auto prefetch_row = [&](int y) {
      if (y < IMG_H) {
        l2_prefetch(gc + (size_t)(y * IMG_W + x0 + 64 * s + 32 * (int)rank) * 96, 32 * 192);
        if (!(y & 1)) l2_prefetch(gp + (size_t)((y >> 1) * (IMG_W / 2) + (x0 >> 1) + 32 * s + 16 * (int)rank) * 96, 16 * 192);
      }
    };
    uint32_t pv[6];
    auto load_p = [&](int py) {
      const uint32_t ro = (uint32_t)min(max(py, 0), IMG_H / 2 - 1) * (IMG_W / 2 * 192);
      const uint4 v4 = ldg128((const char*)gp + (size_t)(poff4 + ro));
      const uint2 v2 = ldg64((const char*)gp + (size_t)(poff2 + ro));
      pv[0] = v4.x; pv[1] = v4.y; pv[2] = v4.z; pv[3] = v4.w; pv[4] = v2.x; pv[5] = v2.y;
    };

    float acc[24];
    uint4 f[3][2];
    const uint32_t cl0 = cbuf + (2 * g + odd) * 192 + q * 16, cl1 = cbuf + (2 * g + (odd ^ 1)) * 192 + q * 16;
    {
      if (pt == 0) {
        for (int k = 0; k < 2; k++) prefetch_row(2 * i0 + k);
        l2_prefetch(gp + (size_t)((i0 + 1) * (IMG_W / 2) + (x0 >> 1) + 32 * s + 16 * (int)rank) * 96, 16 * 192);
      }
      load_p(i0 - 1);
      bar_sync(2, 256);
      mbar_wait(cbar, 0);
      load_frags(f, cl0, cl1);
      fence_async();
      __syncwarp();
      if (lane == 0) tma_row(2 * i0);
      TS(21);
      mbar_wait(bars + BAR_WL * 8, 0);
      TS(22);
#pragma unroll 1
      for (int id = tid - 256; id < 576; id += 256) {
        const int cin = id / 6, c6 = id - 6 * cin;
        const uint4 v = lds128(sb + OFF_U + 9 * U_TILE + (cin >= 48 ? 9 * U_TILE - 9216 : 0) + cin * 192 + chb * 2 + c6 * 16);
        const int ks = 2 * (cin >> 5) + ((cin & 3) >> 1), u = (cin & 7) >> 2, krow = 2 * ((cin & 31) >> 3) + (cin & 1);
        const uint32_t base = sb + OFF_WL + ks * WL_TILE + u * 768 + krow * 16;
        const uint32_t w[4] = {v.x, v.y, v.z, v.w};
#pragma unroll
        for (int wd = 0; wd < 4; wd++) {
          const int qq = c6 < 4 ? c6 : 2 * (c6 - 4) + (wd >> 1);
          const int j = c6 < 4 ? wd : 4 + (wd & 1);
          sts32(base + j * 128 + qq * 4, w[wd]);
        }
      }
      uint4 hf[3][2];
      float hacc[24];
      mbar_wait(hbar, 0);
      TS(23);
      load_frags(hf, hcbuf + min(16 * warp + g, 33) * 192 + q * 16, hcbuf + min(16 * warp + g + 8, 33) * 192 + q * 16);
      fence_async();
      bar_sync(2, 256);
      bar_arrive(6, 512);
      TS(24);
      if (pt == 96) { prefetch_row(2 * i0 + 2); prefetch_row(2 * i0 + 3); }
      lateral_issue(hacc, hf, wl_lo);
      lateral_issue(acc, f, wl_lo);
      wg_wait<1>();
      TS(25);
#pragma unroll
      for (int h = 0; h < 2; h++) {
        const int r = 16 * warp + g + 8 * h, y = 2 * i0 - 1 + r;
        const uint32_t mk = (hx >= 0 && hx < IMG_W && y >= 0 && y < IMG_H) ? 0xffffffffu : 0u;
        if (r < 34) {
          const uint32_t dst = sb + OFF_HM + (s * 34 + r) * 96;
          const uint4 p4 = lds128(dst + q * 16);
          const uint2 p2 = lds64(dst + 64 + q * 8);
          const uint32_t pw[6] = {p4.x, p4.y, p4.z, p4.w, p2.x, p2.y};
          uint32_t d[6];
#pragma unroll
          for (int k = 0; k < 6; k++) d[k] = badd(pack2(hacc[4 * k + 2 * h], hacc[4 * k + 2 * h + 1]), pw[k]) & mk;
          sts128(dst + q * 16, d[0], d[1], d[2], d[3]);
          sts64(dst + 64 + q * 8, d[4], d[5]);
        }
      }
      cluster_wait();
      bar_sync(4 + s, 128);
    }
    TS(1);

    const uint32_t s128_0 = sb + OFF_T + (1 + 64 * s + 16 * warp + 2 * g + odd) * 16 + q * PLANE;
    const uint32_t s128_1 = sb + OFF_T + (1 + 64 * s + 16 * warp + 2 * g + (odd ^ 1)) * 16 + q * PLANE;
    const uint32_t d64 = (4 + (q >> 1) - q) * PLANE + (q & 1) * 8;
    const uint32_t r0off = rank ? TROW : 0, r3off = rank ? 0 : TROW;

    uint32_t st0[2][6], st1[2][6];
#pragma unroll
    for (int k = 0; k < 12; k++) { (&st0[0][0])[k] = 0u; (&st1[0][0])[k] = 0u; }
    auto store_row = [&](uint32_t off, int h, const uint32_t (&v)[6]) {
      const uint32_t ad = (h ? s128_1 : s128_0) + off;
      sts128(ad, v[0], v[1], v[2], v[3]);
      sts64(ad + d64, v[4], v[5]);
    };
    const bool hl = lane < 12;
    const int rho = lane >= 6, tau = rho ^ (int)rank;
    const uint32_t hsa = sb + OFF_HM + (s * 34 + (warp == 2 ? tau : 1 + rho)) * 96 + (lane - 6 * rho) * 16;
    const uint32_t hsb = sb + OFF_HM + (s * 34 + (warp == 2 ? tau + 2 : 2 - rho)) * 96 + (lane - 6 * rho) * 16;
    const uint32_t hdst = sb + OFF_T + (warp == 2 ? PAIR : 0) + rho * TROW + (lane - 6 * rho) * PLANE + (s ? 129 * 16 : 0);
    auto halo_val = [&](int step) {
      const uint32_t sg = (warp == 2 || rho) ? 0xBF80BF80u : 0x3F803F80u;
      const uint4 va = lds128(hsa + step * 192), vb = lds128(hsb + step * 192);
      return make_uint4(bfma(vb.x, sg, va.x), bfma(vb.y, sg, va.y), bfma(vb.z, sg, va.z), bfma(vb.w, sg, va.w));
    };

#pragma unroll 1
    for (int j = 0; j <= STEPS; j++) {
      const int yA = 2 * (i0 + j) - 1;
      const uint32_t ph = (j & 1) ^ 1;
      TS(2 + j);
      uint32_t t0[2][6], t3[2][6];
      wg_wait<0>();
      {
        const uint32_t msk = yA < 0 ? 0u : 0xffffffffu;
#pragma unroll
        for (int h = 0; h < 2; h++)
#pragma unroll
          for (int k = 0; k < 6; k++) {
            const uint32_t d = badd(pack2(acc[4 * k + 2 * h], acc[4 * k + 2 * h + 1]), pv[k]);
            t0[h][k] = bsub(st0[h][k], d);
            st0[h][k] = d & msk;
          }
      }
      load_p(i0 + j);
      bool early = mbar_test(cbar, 1);
      if (early) load_frags(f, cl0, cl1);
      if (j > 0) {
        uint32_t t1[2][6], t2[2][6];
        uint4 hv;
        if (warp == 1 && hl) hv = halo_val(j - 1);
#pragma unroll
        for (int h = 0; h < 2; h++)
#pragma unroll
          for (int k = 0; k < 6; k++) { t1[h][k] = badd(st1[h][k], st0[h][k]); t2[h][k] = bsub(st0[h][k], st1[h][k]); }
        mbar_wait(bars + BAR_EMPTY * 8, ph);
#pragma unroll
        for (int h = 0; h < 2; h++) { store_row(0, h, t1[h]); store_row(TROW, h, t2[h]); }
        if (warp == 1 && hl) sts128(hdst, hv.x, hv.y, hv.z, hv.w);
        __syncwarp();
        if (lane == 0) mbar_arrive(bars + BAR_FULL * 8);
      }
      if (!early) { mbar_wait(cbar, 1); load_frags(f, cl0, cl1); }
      lateral_issue(acc, f, wl_lo);
      if (lane == 0 && j < STEPS) tma_row(yA + 2);
      if (pt == 96 && j + 2 <= STEPS) { prefetch_row(yA + 4); prefetch_row(yA + 5); }
      wg_wait<0>();
      {
        const uint32_t msk = yA + 1 >= IMG_H ? 0u : 0xffffffffu;
        const uint32_t mneg = msk & 0xBF80BF80u;
#pragma unroll
        for (int h = 0; h < 2; h++)
#pragma unroll
          for (int k = 0; k < 6; k++) {
            const uint32_t d = badd(pack2(acc[4 * k + 2 * h], acc[4 * k + 2 * h + 1]), pv[k]);
            t3[h][k] = bfma(d, mneg, st1[h][k]);
            st1[h][k] = d & msk;
          }
      }
      early = j == STEPS || mbar_test(cbar, 0);
      if (early) load_frags(f, cl0, cl1);
      if (j > 0) {
        uint4 hv;
        if (warp == 2 && hl) hv = halo_val(j - 1);
        mbar_wait(bars + (BAR_EMPTY + 1) * 8, ph);
#pragma unroll
        for (int h = 0; h < 2; h++) { store_row(PAIR + r0off, h, t0[h]); store_row(PAIR + r3off, h, t3[h]); }
        if (warp == 2 && hl) sts128(hdst, hv.x, hv.y, hv.z, hv.w);
        __syncwarp();
        if (lane == 0) mbar_arrive(bars + (BAR_FULL + 1) * 8);
      }
      if (!early) { mbar_wait(cbar, 0); load_frags(f, cl0, cl1); }
      lateral_issue(acc, f, wl_lo);
      if (lane == 0 && j < STEPS) tma_row(yA + 3);
    }
    wg_wait<0>();
  }
}

}

extern "C" void kernel_launch(void* const* d_in, const int* in_sizes, int n_in, void* d_out, int out_size) {
  (void)in_sizes; (void)n_in; (void)out_size;
  cudaFuncSetAttribute(fpn_kernel, cudaFuncAttributeMaxDynamicSharedMemorySize, SMEM_BYTES);
  fpn_kernel<<<128, 512, SMEM_BYTES, cudaStreamPerThread>>>(
      (const bf16*)d_in[0], (const bf16*)d_in[1], (const bf16*)d_in[2], (const bf16*)d_in[3], (bf16*)d_out);
}
```
